```python
import torch

def _softmax(x, axis=-1):
    return torch.softmax(x, dim=axis)
def _gelu(x):
    return torch.nn.functional.gelu(x, approximate="tanh")
def _silu(x):
    return torch.nn.functional.silu(x)
def _sigmoid(x):
    return torch.sigmoid(x)
def _layernorm(x, axis=-1, eps=1e-5):
    m = x.mean(dim=axis, keepdim=True)
    v = x.var(dim=axis, keepdim=True, unbiased=False)
    return (x - m) / torch.sqrt(v + eps)
def _scatter_add(tgt, idx, src, axis=0):
    return tgt.clone().index_add_(axis, idx, src)
def _segment_sum(src, seg, n):
    out = torch.zeros((n,) + src.shape[1:], dtype=src.dtype)
    return out.index_add_(0, seg, src)
def _pad(x, pw):
    flat = tuple(v for pair in reversed(pw) for v in pair)
    return torch.nn.functional.pad(x, flat)

kernel_name = 'standalone__gqa_softmax__near_ridge'

def setup_inputs():

    _w = (lambda a: (lambda t: t.to(torch.bfloat16) if t.is_floating_point() else t)(torch.as_tensor(a)))
    B, Hq, Hkv, Sq, Sk, D = 8, 32, 32, 608, 1024, 128
    return {
        "q": _w((lambda *s: torch.randn(*s, dtype=torch.bfloat16) * 0.8)(B, Hq, Sq, D)),
        "k": _w((lambda *s: torch.randn(*s, dtype=torch.bfloat16) * 0.8)(B, Hkv, Sk, D)),
        "v": _w((lambda *s: torch.randn(*s, dtype=torch.bfloat16) * 0.05)(B, Hkv, Sk, D)),
    }

def reference(q, k, v):
    B, Hq, Sq, D = q.shape
    Hkv = k.shape[1]
    rep = Hq // Hkv
    k = (lambda x, n, axis: torch.repeat_interleave(x, n, dim=axis))(k, rep, axis=1)
    v = (lambda x, n, axis: torch.repeat_interleave(x, n, dim=axis))(v, rep, axis=1)
    scale = D ** -0.5
    scores = torch.einsum("bhqd,bhkd->bhqk", q, k) * scale
    p = _softmax(scores, axis=-1)
    return torch.einsum("bhqk,bhkd->bhqd", p, v)
```

```cpp
#include <cuda_runtime.h>
#include <cuda_bf16.h>
#include <cuda.h>
#include <stdint.h>

namespace {

constexpr int BH = 256, SQ = 608, SK = 1024, HD = 128;
constexpr int QT = 5;
constexpr int NTILES = BH * QT;
constexpr int NKB = SK / 128;
constexpr int NST = 3;
constexpr int TILE_BYTES = 128 * HD * 2;
constexpr int STAGE_BYTES = 2 * TILE_BYTES;
constexpr int QO_BYTES = 64 * HD * 2;
constexpr int SM_QO = NST * STAGE_BYTES;
constexpr int SM_BAR = SM_QO + 2 * QO_BYTES;
constexpr int SMEM_BYTES = SM_BAR + 256 + 1024;
constexpr int NTHREADS = 384;

#define CL 1
#define GRID 128
#define CH 4
#define LEAD 4
#define LAG 4
#define ESPLIT 40
#define ESPLIT_B 32
#define OSPLIT 4
#define MAXG 4

__device__ __forceinline__ uint32_t smem_u32(const void* p) { return (uint32_t)__cvta_generic_to_shared(p); }

__device__ __forceinline__ void mbar_init(uint32_t bar, uint32_t cnt) {
    asm volatile("mbarrier.init.shared::cta.b64 [%0], %1;" ::"r"(bar), "r"(cnt) : "memory");
}
__device__ __forceinline__ void mbar_expect_tx(uint32_t bar, uint32_t bytes) {
    asm volatile("mbarrier.arrive.expect_tx.shared::cta.b64 _, [%0], %1;" ::"r"(bar), "r"(bytes) : "memory");
}
__device__ __forceinline__ void mbar_arrive(uint32_t bar) {
    asm volatile("mbarrier.arrive.shared::cta.b64 _, [%0];" ::"r"(bar) : "memory");
}
__device__ __forceinline__ bool mbar_try(uint32_t bar, uint32_t parity) {
    uint32_t ok;
    asm volatile("{\n.reg .pred p;\nmbarrier.try_wait.parity.shared::cta.b64 p, [%1], %2;\nselp.u32 %0, 1, 0, p;\n}\n"
                 : "=r"(ok) : "r"(bar), "r"(parity) : "memory");
    return ok;
}
__device__ __forceinline__ void mbar_wait(uint32_t bar, uint32_t parity) {
    asm volatile(
        "{\n.reg .pred p;\n"
        "WAIT_LOOP:\n"
        "mbarrier.try_wait.parity.shared::cta.b64 p, [%0], %1;\n"
        "@p bra WAIT_DONE;\n"
        "bra WAIT_LOOP;\n"
        "WAIT_DONE:\n}\n" ::"r"(bar), "r"(parity) : "memory");
}
__device__ __forceinline__ void tma_load4(uint32_t dst, const CUtensorMap* tm, uint32_t bar, int row, int half, int bh) {
    asm volatile(
        "cp.async.bulk.tensor.4d.shared::cluster.global.mbarrier::complete_tx::bytes [%0], [%1, {%3, %4, %5, %6}], [%2];"
        ::"r"(dst), "l"(tm), "r"(bar), "r"(0), "r"(row), "r"(half), "r"(bh) : "memory");
}
__device__ __forceinline__ void tma_load4_mc(uint32_t dst, const CUtensorMap* tm, uint32_t bar, int row, int half, int bh, uint16_t mask) {
    asm volatile(
        "cp.async.bulk.tensor.4d.shared::cluster.global.mbarrier::complete_tx::bytes.multicast::cluster [%0], [%1, {%3, %4, %5, %6}], [%2], %7;"
        ::"r"(dst), "l"(tm), "r"(bar), "r"(0), "r"(row), "r"(half), "r"(bh), "h"(mask) : "memory");
}
__device__ __forceinline__ void mbar_arrive_cluster(uint32_t bar) {
    asm volatile("mbarrier.arrive.shared::cluster.b64 _, [%0];" ::"r"(bar) : "memory");
}
__device__ __forceinline__ uint64_t policy_evict_first() {
    uint64_t p; asm("createpolicy.fractional.L2::evict_first.b64 %0, 1.0;" : "=l"(p)); return p;
}
__device__ __forceinline__ void tma_load4_ef(uint32_t dst, const CUtensorMap* tm, uint32_t bar, int row, int half, int bh) {
    asm volatile(
        "cp.async.bulk.tensor.4d.shared::cluster.global.mbarrier::complete_tx::bytes.L2::cache_hint [%0], [%1, {%3, %4, %5, %6}], [%2], %7;"
        ::"r"(dst), "l"(tm), "r"(bar), "r"(0), "r"(row), "r"(half), "r"(bh), "l"(policy_evict_first()) : "memory");
}
__device__ __forceinline__ void tma_store4(uint32_t src, const CUtensorMap* tm, int row, int bh) {
    asm volatile(
        "cp.async.bulk.tensor.4d.global.shared::cta.bulk_group [%1, {%2, %3, %2, %4}], [%0];"
        ::"r"(src), "l"(tm), "r"(0), "r"(row), "r"(bh) : "memory");
}
#define TMA_LOAD_Q tma_load4
#define TMA_LOAD_KV tma_load4
__device__ __forceinline__ void wg_fence() { asm volatile("wgmma.fence.sync.aligned;" ::: "memory"); }
__device__ __forceinline__ void wg_commit() { asm volatile("wgmma.commit_group.sync.aligned;" ::: "memory"); }
template <int N> __device__ __forceinline__ void wg_wait() { asm volatile("wgmma.wait_group.sync.aligned %0;" ::"n"(N) : "memory"); }

__device__ __forceinline__ void bar_sync(int id) { asm volatile("bar.sync %0, 256;" ::"r"(id) : "memory"); }
__device__ __forceinline__ void bar_arrive(int id) { asm volatile("bar.arrive %0, 256;" ::"r"(id) : "memory"); }

#define ACC8(d, o) "+f"(d[o + 0]), "+f"(d[o + 1]), "+f"(d[o + 2]), "+f"(d[o + 3]), "+f"(d[o + 4]), "+f"(d[o + 5]), "+f"(d[o + 6]), "+f"(d[o + 7])
#define ACC64(d) ACC8(d, 0), ACC8(d, 8), ACC8(d, 16), ACC8(d, 24), ACC8(d, 32), ACC8(d, 40), ACC8(d, 48), ACC8(d, 56)
#define REGS64 "{%0,%1,%2,%3,%4,%5,%6,%7,%8,%9,%10,%11,%12,%13,%14,%15,%16,%17,%18,%19,%20,%21,%22,%23,%24,%25,%26,%27,%28,%29,%30,%31," \
               "%32,%33,%34,%35,%36,%37,%38,%39,%40,%41,%42,%43,%44,%45,%46,%47,%48,%49,%50,%51,%52,%53,%54,%55,%56,%57,%58,%59,%60,%61,%62,%63}"

template <int TB>
__device__ __forceinline__ void wgmma_rs(float (&d)[64], const uint32_t* a, uint64_t desc, int scale_d) {
    asm volatile(
        "{\n.reg .pred p;\nsetp.ne.b32 p, %69, 0;\n"
        "wgmma.mma_async.sync.aligned.m64n128k16.f32.bf16.bf16 " REGS64 ", {%64,%65,%66,%67}, %68, p, 1, 1, %70;\n}\n"
        : ACC64(d)
        : "r"(a[0]), "r"(a[1]), "r"(a[2]), "r"(a[3]), "l"(desc), "r"(scale_d), "n"(TB));
}

__device__ __forceinline__ void fence_regs(float (&d)[64]) {
#pragma unroll
    for (int i = 0; i < 64; i++) asm volatile("" : "+f"(d[i])::"memory");
}
__device__ __forceinline__ void fence_regs(uint32_t (&d)[32]) {
#pragma unroll
    for (int i = 0; i < 32; i++) asm volatile("" : "+r"(d[i])::"memory");
}

constexpr uint64_t DESC_K = (1ull << 62) | (64ull << 32) | (1ull << 16);
constexpr uint64_t DESC_V = (1ull << 62) | (64ull << 32) | (1024ull << 16);

__device__ __forceinline__ void issue_qk(float (&s)[64], const uint32_t (&q)[32], uint32_t kaddr) {
    uint64_t desc = DESC_K | (uint64_t)((kaddr & 0x3FFFFu) >> 4);
#pragma unroll
    for (int kk = 0; kk < 8; kk++)
        wgmma_rs<0>(s, &q[kk * 4], desc + (uint64_t)((kk >> 2) * 1024 + (kk & 3) * 2), kk > 0);
    wg_commit();
}
__device__ __forceinline__ void issue_pv(float (&o)[64], const uint32_t (&p)[32], uint32_t vaddr, int acc) {
    uint64_t desc = DESC_V | (uint64_t)((vaddr & 0x3FFFFu) >> 4);
#pragma unroll
    for (int kk = 0; kk < 8; kk++)
        wgmma_rs<1>(o, &p[kk * 4], desc + (uint64_t)(kk * 128), kk > 0 ? 1 : acc);
    wg_commit();
}

constexpr float SCALE_LOG2 = 0.08838834764831845f * 1.4426950408889634f;

__device__ __forceinline__ void row_max(const float (&s)[64], float& c0, float& c1) {
    float x0 = fmaxf(s[0], s[1]), x1 = fmaxf(s[2], s[3]);
    float y0 = fmaxf(s[4], s[5]), y1 = fmaxf(s[6], s[7]);
#pragma unroll
    for (int i = 2; i < MAXG; i += 2) {
        x0 = fmaxf(x0, fmaxf(s[4 * i], s[4 * i + 1]));
        x1 = fmaxf(x1, fmaxf(s[4 * i + 2], s[4 * i + 3]));
        y0 = fmaxf(y0, fmaxf(s[4 * i + 4], s[4 * i + 5]));
        y1 = fmaxf(y1, fmaxf(s[4 * i + 6], s[4 * i + 7]));
    }
    x0 = fmaxf(x0, y0); x1 = fmaxf(x1, y1);
    x0 = fmaxf(x0, __shfl_xor_sync(0xffffffffu, x0, 1));
    x1 = fmaxf(x1, __shfl_xor_sync(0xffffffffu, x1, 1));
    x0 = fmaxf(x0, __shfl_xor_sync(0xffffffffu, x0, 2));
    x1 = fmaxf(x1, __shfl_xor_sync(0xffffffffu, x1, 2));
    c0 = -x0 * SCALE_LOG2; c1 = -x1 * SCALE_LOG2;
}

struct Fence {
    uint32_t t, zero;
    __device__ __forceinline__ void operator()() {
        asm volatile("{\n.reg .pred p;\nsetp.ne.u32 p, %1, 0;\n@p mov.u32 %0, %%clock;\n}\n" : "+r"(t) : "r"(zero) : "memory");
    }
};

__device__ __forceinline__ void sp_fma(float (&s)[64], int e, float c0, float c1) {
    if (e < 64) asm volatile("fma.rn.ftz.f32 %0, %0, %1, %2;" : "+f"(s[e]) : "f"(SCALE_LOG2), "f"((e & 2) ? c1 : c0));
}
__device__ __forceinline__ void sp_add(float (&s)[64], int e, float& l0, float& l1) {
    if (e >= 0 && e < 64) {
        if (e & 2) asm volatile("add.ftz.f32 %0, %0, %1;" : "+f"(l1) : "f"(s[e]));
        else asm volatile("add.ftz.f32 %0, %0, %1;" : "+f"(l0) : "f"(s[e]));
    }
}
__device__ __forceinline__ void sp_cvt(uint32_t& r, float lo, float hi) {
    asm volatile("cvt.rn.bf16x2.f32 %0, %1, %2;" : "=r"(r) : "f"(hi), "f"(lo));
}
template <int E0, int E1, bool CVT, class X>
__device__ __forceinline__ void exp_pipe(float (&s)[64], uint32_t (&p)[32], float c0, float c1, float& l0, float& l1,
                                         Fence& sched_fence, X extra) {
    if (E0 == 0) {
#pragma unroll
        for (int e = 0; e < LEAD; e++) sp_fma(s, e, c0, c1);
    }
    int kdone = 0;
#pragma unroll
    for (int e = E0; e < E1; e++) {
        asm volatile("ex2.approx.ftz.f32 %0, %0;" : "+f"(s[e]));
        sp_fma(s, e + LEAD, c0, c1);
        sp_add(s, e - LAG, l0, l1);
        if (CVT) {
            constexpr int NP = (64 - LAG) / 2;
            int k1 = (e + 1 - E0) * NP / (64 - E0);
            const int kmax = e + 1 - LAG > 0 ? (e + 1 - LAG) / 2 : 0;
            if (k1 > kmax) k1 = kmax;
#pragma unroll
            for (int k = 0; k < 32; k++) if (k >= kdone && k < k1) sp_cvt(p[k], s[2 * k], s[2 * k + 1]);
            if (k1 > kdone) kdone = k1;
        }
        extra(e);
        if ((e + 1) % CH == 0) sched_fence();
    }
    if (E1 == 64) {
#pragma unroll
        for (int e = 64 - LAG; e < 64; e++) sp_add(s, e, l0, l1);
#pragma unroll
        for (int k = 0; k < 32; k++) if (k >= kdone) sp_cvt(p[k], s[2 * k], s[2 * k + 1]);
        sched_fence();
    }
}

__device__ __forceinline__ uint32_t qo_addr(uint32_t lane_addr, int kk) { return (lane_addr + (kk >> 2) * 8192) ^ ((kk & 3) * 32); }
__device__ __forceinline__ void load_q1(uint32_t (&q)[32], uint32_t lane_addr, int kk) {
    asm volatile("ldmatrix.sync.aligned.m8n8.x4.shared.b16 {%0,%1,%2,%3}, [%4];"
                 : "=r"(q[4 * kk]), "=r"(q[4 * kk + 1]), "=r"(q[4 * kk + 2]), "=r"(q[4 * kk + 3]) : "r"(qo_addr(lane_addr, kk)) : "memory");
}
__device__ __forceinline__ float ex2(float x) { float y; asm("ex2.approx.ftz.f32 %0, %1;" : "=f"(y) : "f"(x)); return y; }
__device__ __forceinline__ float rcp(float x) { float y; asm("rcp.approx.ftz.f32 %0, %1;" : "=f"(y) : "f"(x)); return y; }
constexpr float L_LIMIT = 4294967296.f;
__device__ __forceinline__ bool final_inv(float l0, float l1, float& i0, float& i1) {
    l0 += __shfl_xor_sync(0xffffffffu, l0, 1);
    l1 += __shfl_xor_sync(0xffffffffu, l1, 1);
    l0 += __shfl_xor_sync(0xffffffffu, l0, 2);
    l1 += __shfl_xor_sync(0xffffffffu, l1, 2);
    i0 = rcp(l0); i1 = rcp(l1);
    return !(l0 <= L_LIMIT) || !(l1 <= L_LIMIT);
}
__device__ __forceinline__ void stage_o_part(float (&o)[64], float i0, float i1, uint32_t lane_addr, int kk, int part) {
    const float sc = (part & 1) ? i1 : i0;
    asm volatile("mul.ftz.f32 %0, %0, %1;" : "+f"(o[8 * kk + 2 * part]) : "f"(sc));
    asm volatile("mul.ftz.f32 %0, %0, %1;" : "+f"(o[8 * kk + 2 * part + 1]) : "f"(sc));
    if (part == 3) {
        uint32_t r0, r1, r2, r3;
        sp_cvt(r0, o[8 * kk + 0], o[8 * kk + 1]); sp_cvt(r1, o[8 * kk + 2], o[8 * kk + 3]);
        sp_cvt(r2, o[8 * kk + 4], o[8 * kk + 5]); sp_cvt(r3, o[8 * kk + 6], o[8 * kk + 7]);
        asm volatile("stmatrix.sync.aligned.m8n8.x4.shared.b16 [%0], {%1,%2,%3,%4};"
                     ::"r"(qo_addr(lane_addr, kk)), "r"(r0), "r"(r1), "r"(r2), "r"(r3) : "memory");
    }
}
template <int K0, int K1>
__device__ __forceinline__ void stage_o(float (&o)[64], float i0, float i1, uint32_t lane_addr) {
#pragma unroll
    for (int kk = K0; kk < K1; kk++)
#pragma unroll
        for (int part = 0; part < 4; part++) stage_o_part(o, i0, i1, lane_addr, kk, part);
}
__device__ __forceinline__ void publish_o(uint32_t bar, int lane) {
    asm volatile("fence.proxy.async.shared::cta;" ::: "memory");
    __syncwarp();
    if (lane == 0) mbar_arrive(bar);
}

#define RELEASE() do { if (lane < CL) mbar_arrive_cluster(empty_addr + 8 * r.st); } while (0)
#define PP_SYNC() bar_sync(my_bar)
#define PP_ARRIVE() bar_arrive(other_bar)

struct Ring {
    uint32_t st, ph;
    __device__ __forceinline__ void next() { if (++st == NST) { st = 0; ph ^= 1; } }
};

struct Tile { int head, qt; bool shared; };
__device__ __forceinline__ Tile get_tile(int u, int rank) {
    const int g = u / 5, k = u - 5 * g;
    if (CL == 1) return Tile{g, k, false};
    if (k == 2) return Tile{g * CL + rank, 4, false};
    const int f = (k < 2 ? k : k - 1) * CL + rank;
    return Tile{g * CL + (f >> 2), f & 3, true};
}
constexpr int NITEMS = NTILES / CL;
constexpr int SL_ROWS = CL == 4 ? 64 : 128;
constexpr int NSL = CL == 4 ? 4 : 2;

__device__ __forceinline__ void load_kv(uint32_t dst, const CUtensorMap* tm, uint32_t bar, int blk, Tile t, int rank) {
    if (CL > 1 && t.shared) {
        tma_load4_mc(dst + (rank & 1) * 16384 + (rank >> 1) * 8192, tm, bar, blk * 128 + (rank >> 1) * 64, rank & 1, t.head, (uint16_t)((1 << CL) - 1));
    } else {
#pragma unroll
        for (int i = 0; i < NSL; i++)
            TMA_LOAD_KV(dst + (i & 1) * 16384 + (i >> 1) * 8192, tm, bar, blk * 128 + (i >> 1) * 64, i & 1, t.head);
    }
}

__global__ void __launch_bounds__(NTHREADS, 1)
attn_kernel(const __grid_constant__ CUtensorMap tmQ, const __grid_constant__ CUtensorMap tmK,
            const __grid_constant__ CUtensorMap tmV, const __grid_constant__ CUtensorMap tmO, const uint32_t zero) {
    extern __shared__ uint8_t smem_raw[];
    const uint32_t smem = (smem_u32(smem_raw) + 1023u) & ~1023u;
    const uint32_t bar_full = smem + SM_BAR, bar_empty = bar_full + 8 * NST;
    const uint32_t bar_q = bar_empty + 8 * NST, bar_o = bar_q + 16, bar_done = bar_o + 16, bar_fb = bar_done + 8;
    const uint32_t bar_wd = bar_fb + 8, sm_flag = bar_wd + 8;
    const int warp = __shfl_sync(0xffffffffu, threadIdx.x >> 5, 0);
    const int lane = threadIdx.x & 31;
    const int rank = blockIdx.x % CL, cid = blockIdx.x / CL, ncl = gridDim.x / CL;
    const int ntiles = (NITEMS - cid + ncl - 1) / ncl;

    if (threadIdx.x == 256) {
        for (int i = 0; i < NST; i++) { mbar_init(bar_full + 8 * i, 1); mbar_init(bar_empty + 8 * i, 8 * CL); }
        for (int i = 0; i < 2; i++) { mbar_init(bar_q + 8 * i, 1); mbar_init(bar_o + 8 * i, 4); }
        mbar_init(bar_done, 2); mbar_init(bar_fb, 1); mbar_init(bar_wd, 8);
        asm volatile("st.shared.u32 [%0], %1;" ::"r"(sm_flag), "r"(0) : "memory");
        asm volatile("fence.mbarrier_init.release.cluster;" ::: "memory");
        asm volatile("fence.proxy.async.shared::cta;" ::: "memory");
        Tile t = get_tile(cid, rank);
        t.shared = false;
        mbar_expect_tx(bar_full, TILE_BYTES);
        load_kv(smem, &tmK, bar_full, 0, t, rank);
        for (int w = 0; w < 2; w++) {
            mbar_expect_tx(bar_q + 8 * w, QO_BYTES);
            TMA_LOAD_Q(smem + SM_QO + w * QO_BYTES, &tmQ, bar_q + 8 * w, t.qt * 128 + w * 64, 0, t.head);
        }
    }
    __syncwarp();
    if (CL > 1) {
        asm volatile("barrier.cluster.arrive.release.aligned;" ::: "memory");
        asm volatile("barrier.cluster.wait.acquire.aligned;" ::: "memory");
    } else {
        __syncthreads();
    }

    if (warp >= 8) {
        asm volatile("setmaxnreg.dec.sync.aligned.u32 24;");
        if (warp == 8) {
            if (lane == 0) {
                Ring r{1, 1};
                const int nsteps = ntiles * NKB;
                Tile tv = get_tile(cid, rank), tk = tv;
                for (int i = 0; i < nsteps; i++) {
                    const uint32_t full = bar_full + 8 * r.st, dst = smem + r.st * STAGE_BYTES;
                    const bool has_k = i + 1 < nsteps;
                    if ((i & 7) == 7) tk = get_tile(cid + ((i + 1) >> 3) * ncl, rank);
                    mbar_wait(bar_empty + 8 * r.st, r.ph);
                    mbar_expect_tx(full, has_k ? STAGE_BYTES : TILE_BYTES);
                    if (has_k) load_kv(dst, &tmK, full, (i + 1) & 7, tk, rank);
                    load_kv(dst + TILE_BYTES, &tmV, full, i & 7, tv, rank);
                    tv = tk;
                    r.next();
                }
            }
            __syncwarp();
            if (CL > 1) {
                asm volatile("barrier.cluster.arrive.relaxed.aligned;" ::: "memory");
                asm volatile("barrier.cluster.wait.aligned;" ::: "memory");
            }
        } else if (warp < 11) {
            if (lane == 0) {
                const int w = warp - 9;
                const uint32_t qo = smem + SM_QO + w * QO_BYTES;
                asm volatile("prefetch.tensormap [%0];" ::"l"(&tmO) : "memory");
#pragma unroll 1
                for (int it = 0; it <= ntiles; it++) {
                    mbar_wait(bar_o + 8 * w, it & 1);
                    if (it > 0) {
                        const Tile t = get_tile(cid + (it - 1) * ncl, rank);
                        tma_store4(qo, &tmO, t.qt * 128 + w * 64, t.head);
                        asm volatile("cp.async.bulk.commit_group;" ::: "memory");
                        asm volatile("cp.async.bulk.wait_group.read 0;" ::: "memory");
                    }
                    if (it + 1 < ntiles) {
                        const Tile t = get_tile(cid + (it + 1) * ncl, rank);
                        mbar_expect_tx(bar_q + 8 * w, QO_BYTES);
                        TMA_LOAD_Q(qo, &tmQ, bar_q + 8 * w, t.qt * 128 + w * 64, 0, t.head);
                    }
                }
                asm volatile("cp.async.bulk.wait_group 0;" ::: "memory");
                mbar_arrive(bar_done);
            }
        } else {
        }
    } else {
        asm volatile("setmaxnreg.inc.sync.aligned.u32 240;");
        const int wg = warp >> 2;
        const uint32_t qbar = bar_q + 8 * wg, obar = bar_o + 8 * wg;
        const uint32_t lrow = (warp & 3) * 16 + (lane & 7) + ((lane >> 3) & 1) * 8;
        const uint32_t lane_addr = smem + SM_QO + wg * QO_BYTES + lrow * 128 + (((lane >> 4) ^ (lane & 7)) << 4);
        const int my_bar = 1 + wg, other_bar = 2 - wg;
        uint32_t empty_addr = bar_empty;
        if (CL > 1) asm("mapa.shared::cluster.u32 %0, %1, %2;" : "=r"(empty_addr) : "r"(bar_empty), "r"(lane % CL));
        uint32_t redo = 0;

        float s[64], o[64];
        uint32_t p[32], q[32];
        float c0, c1, l0 = 0.f, l1 = 0.f, i0 = 0.f, i1 = 0.f;
        Ring r{0, 0};
        Fence sched_fence{0u, zero};
        auto none = [](int) {};
#pragma unroll
        for (int i = 0; i < 64; i++) o[i] = 0.f;
        if (wg == 1) bar_arrive(1);
        mbar_wait(qbar, 0);
#pragma unroll
        for (int kk = 0; kk < 8; kk++) load_q1(q, lane_addr, kk);
        mbar_wait(bar_full + 8 * r.st, r.ph);
        PP_SYNC();
        fence_regs(q);
        wg_fence();
        issue_qk(s, q, smem + r.st * STAGE_BYTES);
        PP_ARRIVE();
        wg_wait<0>();
        fence_regs(s);
        RELEASE();
        r.next();
        row_max(s, c0, c1);
        exp_pipe<0, 64, true>(s, p, c0, c1, l0, l1, sched_fence, none);
        fence_regs(p);
        mbar_wait(bar_full + 8 * r.st, r.ph);
        PP_SYNC();

#define STEP_HEAD()                                                               \
                                                                            \
        fence_regs(s); fence_regs(o); fence_regs(p); fence_regs(q);               \
        wg_fence();                                                               \
        issue_qk(s, q, smem + r.st * STAGE_BYTES);                                \
                                                                            \
        issue_pv(o, p, smem + r.st * STAGE_BYTES + TILE_BYTES, 1);                \
        PP_ARRIVE();                                                              \

#define STEP_WAIT_QK()                                                            \
        wg_wait<1>();                                                             \
                                                                            \
        fence_regs(s); fence_regs(q);
#define STEP_TAIL(ES, XA, XB, POST)                                               \
        exp_pipe<0, ES, false>(s, p, c0, c1, l0, l1, sched_fence, XA);            \
                                                                            \
        wg_wait<0>();                                                             \
                                                                            \
        fence_regs(o); fence_regs(p);                                             \
        RELEASE();                                                                \
        r.next();                                                                 \
        exp_pipe<ES, 64, true>(s, p, c0, c1, l0, l1, sched_fence, XB);            \
        fence_regs(p);                                                            \
        POST                                                                      \
        mbar_wait(bar_full + 8 * r.st, r.ph);                                     \
                                                                            \
        PP_SYNC();                                                                \
                                                                            \

        for (int it = 0; it < ntiles; it++) {
            {
                fence_regs(s);
                wg_fence();
                issue_qk(s, q, smem + r.st * STAGE_BYTES);
                sched_fence();
                stage_o<OSPLIT, 8>(o, i0, i1, lane_addr);
                fence_regs(o); fence_regs(p);
                wg_fence();
                issue_pv(o, p, smem + r.st * STAGE_BYTES + TILE_BYTES, 0);
                PP_ARRIVE();
                STEP_WAIT_QK()
                STEP_TAIL(ESPLIT, none, none, publish_o(obar, lane);)
            }
#pragma unroll 1
            for (int j = 1; j < NKB - 2; j++) {
                STEP_HEAD()
                STEP_WAIT_QK()
                STEP_TAIL(ESPLIT, none, none, )
            }
            if (it + 1 < ntiles) {
                {
                    STEP_HEAD()
                    mbar_wait(qbar, (it + 1) & 1);
                    STEP_WAIT_QK()
                    auto ldq = [&](int e) { if (e % 4 == 3 && e < 32) load_q1(q, lane_addr, e / 4); };
                    STEP_TAIL(ESPLIT, ldq, none, )
                }
                {
                    STEP_HEAD()
                    if (final_inv(l0, l1, i0, i1)) redo |= 1u << it;
                    STEP_WAIT_QK()
                    row_max(s, c0, c1);
                    l0 = l1 = 0.f;
                    auto sto = [&](int e) {
                        constexpr int N = OSPLIT * 4, R = 64 - ESPLIT_B;
                        const int a = (e - ESPLIT_B) * N / R, b = (e + 1 - ESPLIT_B) * N / R;
#pragma unroll
                        for (int u = 0; u < N; u++) if (u >= a && u < b) stage_o_part(o, i0, i1, lane_addr, u / 4, u % 4);
                    };
                    STEP_TAIL(ESPLIT_B, none, sto, )
                }
            } else {
                {
                    STEP_HEAD()
                    STEP_WAIT_QK()
                    STEP_TAIL(ESPLIT, none, none, )
                }
                fence_regs(o); fence_regs(p);
                wg_fence();
                issue_pv(o, p, smem + r.st * STAGE_BYTES + TILE_BYTES, 1);
                if (wg == 0) { PP_ARRIVE(); }
                if (final_inv(l0, l1, i0, i1)) redo |= 1u << it;
                wg_wait<0>();
                fence_regs(o);
                stage_o<0, 8>(o, i0, i1, lane_addr);
                publish_o(obar, lane);
            }
        }
        if (zero) asm volatile("st.shared.u32 [%0], %1;" ::"r"(lane_addr), "r"(sched_fence.t) : "memory");

        if (redo) asm volatile("red.shared.or.b32 [%0], %1;" ::"r"(sm_flag), "r"(redo) : "memory");
        bar_sync(3);
        asm volatile("ld.shared.u32 %0, [%1];" : "=r"(redo) : "r"(sm_flag) : "memory");
        redo = __shfl_sync(0xffffffffu, redo, 0);
        if (redo) {
            mbar_wait(bar_done, 0);
            uint32_t ph = 0;
#pragma unroll 1
            for (int it = 0; it < ntiles; it++) {
                if (!((redo >> it) & 1)) continue;
                Tile t = get_tile(cid + it * ncl, rank);
                t.shared = false;
                float m0 = -INFINITY, m1 = -INFINITY;
                l0 = l1 = 0.f;
#pragma unroll
                for (int i = 0; i < 64; i++) o[i] = 0.f;
#pragma unroll 1
                for (int j = 0; j < NKB; j++) {
                    if (threadIdx.x == 0) {
                        mbar_expect_tx(bar_fb, j == 0 ? STAGE_BYTES + 2 * QO_BYTES : STAGE_BYTES);
                        if (j == 0)
                            for (int w = 0; w < 2; w++) tma_load4(smem + SM_QO + w * QO_BYTES, &tmQ, bar_fb, t.qt * 128 + w * 64, 0, t.head);
                        load_kv(smem, &tmK, bar_fb, j, t, rank);
                        load_kv(smem + TILE_BYTES, &tmV, bar_fb, j, t, rank);
                    }
                    __syncwarp();
                    mbar_wait(bar_fb, ph); ph ^= 1;
#pragma unroll
                    for (int kk = 0; kk < 8; kk++) load_q1(q, lane_addr, kk);
                    fence_regs(q); fence_regs(s);
                    wg_fence();
                    issue_qk(s, q, smem);
                    wg_wait<0>();
                    fence_regs(s);
                    float x0 = m0, x1 = m1;
#pragma unroll
                    for (int i = 0; i < 16; i++) {
                        x0 = fmaxf(x0, fmaxf(s[4 * i], s[4 * i + 1]));
                        x1 = fmaxf(x1, fmaxf(s[4 * i + 2], s[4 * i + 3]));
                    }
                    x0 = fmaxf(x0, __shfl_xor_sync(0xffffffffu, x0, 1)); x1 = fmaxf(x1, __shfl_xor_sync(0xffffffffu, x1, 1));
                    x0 = fmaxf(x0, __shfl_xor_sync(0xffffffffu, x0, 2)); x1 = fmaxf(x1, __shfl_xor_sync(0xffffffffu, x1, 2));
                    const float r0 = x0 == -INFINITY ? 0.f : x0, r1 = x1 == -INFINITY ? 0.f : x1;
                    const float a0 = ex2((m0 - r0) * SCALE_LOG2), a1 = ex2((m1 - r1) * SCALE_LOG2);
                    m0 = x0; m1 = x1;
                    l0 *= a0; l1 *= a1;
#pragma unroll
                    for (int i = 0; i < 64; i++) {
                        s[i] = ex2((s[i] - ((i & 2) ? r1 : r0)) * SCALE_LOG2);
                        if (i & 2) l1 += s[i]; else l0 += s[i];
                        o[i] *= (i & 2) ? a1 : a0;
                    }
#pragma unroll
                    for (int k = 0; k < 32; k++) sp_cvt(p[k], s[2 * k], s[2 * k + 1]);
                    fence_regs(o); fence_regs(p);
                    wg_fence();
                    issue_pv(o, p, smem + TILE_BYTES, 1);
                    wg_wait<0>();
                    fence_regs(o);
                    bar_sync(3);
                }
                final_inv(l0, l1, i0, i1);
                stage_o<0, 8>(o, i0, i1, lane_addr);
                asm volatile("fence.proxy.async.shared::cta;" ::: "memory");
                bar_sync(3);
                if (threadIdx.x == 0) {
                    for (int w = 0; w < 2; w++) tma_store4(smem + SM_QO + w * QO_BYTES, &tmO, t.qt * 128 + w * 64, t.head);
                    asm volatile("cp.async.bulk.commit_group;" ::: "memory");
                    asm volatile("cp.async.bulk.wait_group 0;" ::: "memory");
                }
                __syncwarp();
            }
        }
    }
}

typedef CUresult (*EncodeFn)(CUtensorMap*, CUtensorMapDataType, cuuint32_t, void*, const cuuint64_t*, const cuuint64_t*,
                             const cuuint32_t*, const cuuint32_t*, CUtensorMapInterleave, CUtensorMapSwizzle,
                             CUtensorMapL2promotion, CUtensorMapFloatOOBfill);

void make_map(EncodeFn enc, CUtensorMap* tm, void* ptr, int rows, int box_rows, int box_halves) {
    cuuint64_t dims[4] = {64, (cuuint64_t)rows, 2, (cuuint64_t)BH};
    cuuint64_t strides[3] = {HD * 2, 128, (cuuint64_t)rows * HD * 2};
    cuuint32_t box[4] = {64, (cuuint32_t)box_rows, (cuuint32_t)box_halves, 1};
    cuuint32_t es[4] = {1, 1, 1, 1};
    enc(tm, CU_TENSOR_MAP_DATA_TYPE_BFLOAT16, 4, ptr, dims, strides, box, es, CU_TENSOR_MAP_INTERLEAVE_NONE,
        CU_TENSOR_MAP_SWIZZLE_128B, CU_TENSOR_MAP_L2_PROMOTION_L2_256B, CU_TENSOR_MAP_FLOAT_OOB_FILL_NONE);
}

}

extern "C" void kernel_launch(void* const* d_in, const int* in_sizes, int n_in, void* d_out, int out_size) {
    static EncodeFn enc = nullptr;
    static int nsm = 0;
    if (!enc) {
        void* fn = nullptr;
        cudaDriverEntryPointQueryResult qr;
        cudaGetDriverEntryPoint("cuTensorMapEncodeTiled", &fn, cudaEnableDefault, &qr);
        enc = (EncodeFn)fn;
        cudaFuncSetAttribute(attn_kernel, cudaFuncAttributeMaxDynamicSharedMemorySize, SMEM_BYTES);
        int dev = 0;
        cudaGetDevice(&dev);
        cudaDeviceGetAttribute(&nsm, cudaDevAttrMultiProcessorCount, dev);
    }
    CUtensorMap tq, tk, tv, to;
    make_map(enc, &tq, d_in[0], SQ, 64, 2);
    make_map(enc, &tk, d_in[1], SK, SL_ROWS, 1);
    make_map(enc, &tv, d_in[2], SK, SL_ROWS, 1);
    make_map(enc, &to, d_out, SQ, 64, 2);
    cudaLaunchConfig_t cfg = {};
    cfg.gridDim = dim3(GRID); cfg.blockDim = dim3(NTHREADS); cfg.dynamicSmemBytes = SMEM_BYTES; cfg.stream = cudaStreamPerThread;
    cudaLaunchAttribute attr;
    attr.id = cudaLaunchAttributeClusterDimension;
    attr.val.clusterDim.x = CL; attr.val.clusterDim.y = 1; attr.val.clusterDim.z = 1;
    cfg.attrs = &attr; cfg.numAttrs = CL > 1 ? 1 : 0;
    cudaLaunchKernelEx(&cfg, attn_kernel, tq, tk, tv, to, 0u);
}
```

```cpp
#include <cuda_runtime.h>
#include <cuda_bf16.h>
#include <cuda.h>
#include <stdint.h>

namespace {

constexpr int BH = 256, SQ = 608, SK = 1024, HD = 128;
constexpr int QT = 5;
constexpr int NKB = SK / 128;
constexpr int NST = 3;
constexpr int TILE_BYTES = 128 * HD * 2;
constexpr int STAGE_BYTES = 2 * TILE_BYTES;
constexpr int QO_BYTES = 64 * HD * 2;
constexpr int SM_QO = NST * STAGE_BYTES;
constexpr int SM_BAR = SM_QO + 2 * QO_BYTES;
constexpr int SM_ST = SM_BAR + 256;
constexpr int ST_BYTES = 64 * 8;
constexpr int SMEM_BYTES = SM_ST + 2 * ST_BYTES;
constexpr int NTHREADS = 384;

constexpr int NM = 128, NT = 10;
constexpr int NGRP = 25;
constexpr int NX = NM - NGRP * QT, NREG = NGRP * NT;
constexpr int NH = 4, HB = 2, NPC = NM / NH;
constexpr int HELPER_DELAY_NS = 1500;
static_assert(NM * NT == BH * QT && HB == 2, "schedule");
constexpr int QSLOT0 = 5, QSLOT1 = 6;
constexpr int CH = 4;
constexpr int LEAD = 4;
constexpr int LAG = 6;
constexpr int ESPLIT = 40;
constexpr int ESPLIT_B = 32;
constexpr int OSPLIT = 4;
constexpr int MAXG = 4;

__device__ __forceinline__ uint32_t smem_u32(const void* p) { return (uint32_t)__cvta_generic_to_shared(p); }

__device__ __forceinline__ void mbar_init(uint32_t bar, uint32_t cnt) {
    asm volatile("mbarrier.init.shared::cta.b64 [%0], %1;" ::"r"(bar), "r"(cnt) : "memory");
}
__device__ __forceinline__ void mbar_expect_tx(uint32_t bar, uint32_t bytes) {
    asm volatile("mbarrier.arrive.expect_tx.shared::cta.b64 _, [%0], %1;" ::"r"(bar), "r"(bytes) : "memory");
}
__device__ __forceinline__ void mbar_expect_tx_only(uint32_t bar, uint32_t bytes) {
    asm volatile("mbarrier.expect_tx.relaxed.cta.shared::cta.b64 [%0], %1;" ::"r"(bar), "r"(bytes) : "memory");
}
__device__ __forceinline__ void mbar_arrive(uint32_t bar) {
    asm volatile("mbarrier.arrive.shared::cta.b64 _, [%0];" ::"r"(bar) : "memory");
}
__device__ __forceinline__ void mbar_wait(uint32_t bar, uint32_t parity) {
    asm volatile(
        "{\n.reg .pred p;\n"
        "WAIT_LOOP:\n"
        "mbarrier.try_wait.parity.shared::cta.b64 p, [%0], %1;\n"
        "@p bra WAIT_DONE;\n"
        "bra WAIT_LOOP;\n"
        "WAIT_DONE:\n}\n" ::"r"(bar), "r"(parity) : "memory");
}
__device__ __forceinline__ void mbar_wait_sleep(uint32_t bar, uint32_t parity) {
    asm volatile(
        "{\n.reg .pred p;\n"
        "WAIT_LOOP:\n"
        "mbarrier.try_wait.parity.shared::cta.b64 p, [%0], %1, %2;\n"
        "@p bra WAIT_DONE;\n"
        "bra WAIT_LOOP;\n"
        "WAIT_DONE:\n}\n" ::"r"(bar), "r"(parity), "r"(20000) : "memory");
}
__device__ __forceinline__ uint64_t policy_evict_first() {
    uint64_t p; asm("createpolicy.fractional.L2::evict_first.b64 %0, 1.0;" : "=l"(p)); return p;
}
__device__ __forceinline__ void load_q_tile(uint32_t dst, const CUtensorMap* tm, uint32_t bar, int row, int bh) {
    asm volatile(
        "cp.async.bulk.tensor.5d.shared::cluster.global.mbarrier::complete_tx::bytes.L2::cache_hint [%0], [%1, {%3, %3, %3, %4, %5}], [%2], %6;"
        ::"r"(dst), "l"(tm), "r"(bar), "r"(0), "r"(row >> 3), "r"(bh), "l"(policy_evict_first()) : "memory");
}
__device__ __forceinline__ void load_o_tile(uint32_t dst, const CUtensorMap* tm, uint32_t bar, int row, int bh) {
    asm volatile(
        "cp.async.bulk.tensor.5d.shared::cluster.global.mbarrier::complete_tx::bytes [%0], [%1, {%3, %3, %3, %4, %5}], [%2];"
        ::"r"(dst), "l"(tm), "r"(bar), "r"(0), "r"(row >> 3), "r"(bh) : "memory");
}
__device__ __forceinline__ void store_o_tile(uint32_t src, const CUtensorMap* tm, int row, int bh) {
    asm volatile(
        "cp.async.bulk.tensor.5d.global.shared::cta.bulk_group [%1, {%2, %2, %2, %3, %4}], [%0];"
        ::"r"(src), "l"(tm), "r"(0), "r"(row >> 3), "r"(bh) : "memory");
}
__device__ __forceinline__ void wg_fence() { asm volatile("wgmma.fence.sync.aligned;" ::: "memory"); }
__device__ __forceinline__ void wg_commit() { asm volatile("wgmma.commit_group.sync.aligned;" ::: "memory"); }
template <int N> __device__ __forceinline__ void wg_wait() { asm volatile("wgmma.wait_group.sync.aligned %0;" ::"n"(N) : "memory"); }

__device__ __forceinline__ void bar_sync(int id) { asm volatile("bar.sync %0, 256;" ::"r"(id) : "memory"); }
__device__ __forceinline__ void bar_arrive(int id) { asm volatile("bar.arrive %0, 256;" ::"r"(id) : "memory"); }

#define ACC8(d, o) "+f"(d[o + 0]), "+f"(d[o + 1]), "+f"(d[o + 2]), "+f"(d[o + 3]), "+f"(d[o + 4]), "+f"(d[o + 5]), "+f"(d[o + 6]), "+f"(d[o + 7])
#define ACC64(d) ACC8(d, 0), ACC8(d, 8), ACC8(d, 16), ACC8(d, 24), ACC8(d, 32), ACC8(d, 40), ACC8(d, 48), ACC8(d, 56)
#define REGS64 "{%0,%1,%2,%3,%4,%5,%6,%7,%8,%9,%10,%11,%12,%13,%14,%15,%16,%17,%18,%19,%20,%21,%22,%23,%24,%25,%26,%27,%28,%29,%30,%31," \
               "%32,%33,%34,%35,%36,%37,%38,%39,%40,%41,%42,%43,%44,%45,%46,%47,%48,%49,%50,%51,%52,%53,%54,%55,%56,%57,%58,%59,%60,%61,%62,%63}"

template <int TB>
__device__ __forceinline__ void wgmma_rs(float (&d)[64], const uint32_t* a, uint64_t desc, int scale_d) {
    asm volatile(
        "{\n.reg .pred p;\nsetp.ne.b32 p, %69, 0;\n"
        "wgmma.mma_async.sync.aligned.m64n128k16.f32.bf16.bf16 " REGS64 ", {%64,%65,%66,%67}, %68, p, 1, 1, %70;\n}\n"
        : ACC64(d)
        : "r"(a[0]), "r"(a[1]), "r"(a[2]), "r"(a[3]), "l"(desc), "r"(scale_d), "n"(TB));
}

template <int H>
__device__ __forceinline__ void wgmma_rs_half(float (&d)[64], const uint32_t* a, uint64_t desc, int scale_d) {
    asm volatile(
        "{\n.reg .pred p;\nsetp.ne.b32 p, %37, 0;\n"
        "wgmma.mma_async.sync.aligned.m64n64k16.f32.bf16.bf16 "
        "{%0,%1,%2,%3,%4,%5,%6,%7,%8,%9,%10,%11,%12,%13,%14,%15,%16,%17,%18,%19,%20,%21,%22,%23,%24,%25,%26,%27,%28,%29,%30,%31}"
        ", {%32,%33,%34,%35}, %36, p, 1, 1, 0;\n}\n"
        : ACC8(d, 32 * H), ACC8(d, 32 * H + 8), ACC8(d, 32 * H + 16), ACC8(d, 32 * H + 24)
        : "r"(a[0]), "r"(a[1]), "r"(a[2]), "r"(a[3]), "l"(desc), "r"(scale_d));
}
template <int H>
__device__ __forceinline__ void fence_half(float (&d)[64]) {
#pragma unroll
    for (int i = 0; i < 32; i++) asm volatile("" : "+f"(d[32 * H + i])::"memory");
}

__device__ __forceinline__ void fence_regs(float (&d)[64]) {
#pragma unroll
    for (int i = 0; i < 64; i++) asm volatile("" : "+f"(d[i])::"memory");
}
__device__ __forceinline__ void fence_regs(uint32_t (&d)[32]) {
#pragma unroll
    for (int i = 0; i < 32; i++) asm volatile("" : "+r"(d[i])::"memory");
}

constexpr uint64_t DESC_K = (1ull << 62) | (128ull << 32) | (1ull << 16);
constexpr uint64_t DESC_V = (1ull << 62) | (128ull << 32) | (64ull << 16);
constexpr int K_HALF = 64, V_STEP = 256;

__device__ __forceinline__ void issue_qk(float (&s)[64], const uint32_t (&q)[32], uint32_t kaddr) {
    uint64_t desc = DESC_K | (uint64_t)((kaddr & 0x3FFFFu) >> 4);
#pragma unroll
    for (int kk = 0; kk < 8; kk++)
        wgmma_rs<0>(s, &q[kk * 4], desc + (uint64_t)((kk >> 2) * K_HALF + (kk & 3) * 2), kk > 0);
    wg_commit();
}
template <int H>
__device__ __forceinline__ void issue_qk_half(float (&s)[64], const uint32_t (&q)[32], uint32_t kaddr) {
    uint64_t desc = DESC_K | (uint64_t)(((kaddr + H * (TILE_BYTES / 2)) & 0x3FFFFu) >> 4);
#pragma unroll
    for (int kk = 0; kk < 8; kk++)
        wgmma_rs_half<H>(s, &q[kk * 4], desc + (uint64_t)((kk >> 2) * K_HALF + (kk & 3) * 2), kk > 0);
    wg_commit();
}
__device__ __forceinline__ void issue_pv(float (&o)[64], const uint32_t (&p)[32], uint32_t vaddr, int acc) {
    uint64_t desc = DESC_V | (uint64_t)((vaddr & 0x3FFFFu) >> 4);
#pragma unroll
    for (int kk = 0; kk < 8; kk++)
        wgmma_rs<1>(o, &p[kk * 4], desc + (uint64_t)(kk * V_STEP), kk > 0 ? 1 : acc);
    wg_commit();
}

constexpr float SCALE_LOG2 = 0.08838834764831845f * 1.4426950408889634f;

__device__ __forceinline__ void row_ref(const float (&s)[64], float& c0, float& c1) {
    float x0 = fmaxf(s[0], s[1]), x1 = fmaxf(s[2], s[3]);
    float y0 = fmaxf(s[4], s[5]), y1 = fmaxf(s[6], s[7]);
#pragma unroll
    for (int i = 2; i < MAXG; i += 2) {
        x0 = fmaxf(x0, fmaxf(s[4 * i], s[4 * i + 1]));
        x1 = fmaxf(x1, fmaxf(s[4 * i + 2], s[4 * i + 3]));
        y0 = fmaxf(y0, fmaxf(s[4 * i + 4], s[4 * i + 5]));
        y1 = fmaxf(y1, fmaxf(s[4 * i + 6], s[4 * i + 7]));
    }
    x0 = fmaxf(x0, y0); x1 = fmaxf(x1, y1);
    x0 = fmaxf(x0, __shfl_xor_sync(0xffffffffu, x0, 1));
    x1 = fmaxf(x1, __shfl_xor_sync(0xffffffffu, x1, 1));
    x0 = fmaxf(x0, __shfl_xor_sync(0xffffffffu, x0, 2));
    x1 = fmaxf(x1, __shfl_xor_sync(0xffffffffu, x1, 2));
    c0 = -x0 * SCALE_LOG2; c1 = -x1 * SCALE_LOG2;
}

struct Fence {
    uint32_t t, zero;
    __device__ __forceinline__ void operator()() {
        asm volatile("{\n.reg .pred p;\nsetp.ne.u32 p, %1, 0;\n@p mov.u32 %0, %%clock;\n}\n" : "+r"(t) : "r"(zero) : "memory");
    }
};

__device__ __forceinline__ void sp_fma(float (&s)[64], int e, float c0, float c1) {
    if (e < 64) asm volatile("fma.rn.ftz.f32 %0, %0, %1, %2;" : "+f"(s[e]) : "f"(SCALE_LOG2), "f"((e & 2) ? c1 : c0));
}
__device__ __forceinline__ void sp_add(float (&s)[64], int e, float& l0, float& l1) {
    if (e >= 0 && e < 64) {
        if (e & 2) asm volatile("add.ftz.f32 %0, %0, %1;" : "+f"(l1) : "f"(s[e]));
        else asm volatile("add.ftz.f32 %0, %0, %1;" : "+f"(l0) : "f"(s[e]));
    }
}
__device__ __forceinline__ void sp_cvt(uint32_t& r, float lo, float hi) {
    asm volatile("cvt.rn.bf16x2.f32 %0, %1, %2;" : "=r"(r) : "f"(hi), "f"(lo));
}
template <int E0, int E1, bool CVT, int CV0 = E0, class X>
__device__ __forceinline__ void exp_pipe(float (&s)[64], uint32_t (&p)[32], float c0, float c1, float& l0, float& l1,
                                         Fence& sched_fence, X extra) {
    if (E0 == 0) {
#pragma unroll
        for (int e = 0; e < LEAD; e++) sp_fma(s, e, c0, c1);
    }
    int kdone = 0;
    if (CV0 < E0) {
        kdone = (E0 - CV0) * ((64 - LAG) / 2) / (64 - CV0);
        if (kdone > (E0 - LAG) / 2) kdone = (E0 - LAG) / 2;
    }
#pragma unroll
    for (int e = E0; e < E1; e++) {
        asm volatile("ex2.approx.ftz.f32 %0, %0;" : "+f"(s[e]));
        sp_fma(s, e + LEAD, c0, c1);
        sp_add(s, e - LAG, l0, l1);
        if (CVT) {
            constexpr int NP = (64 - LAG) / 2;
            int k1 = (e + 1 - CV0) * NP / (64 - CV0);
            const int kmax = e + 1 - LAG > 0 ? (e + 1 - LAG) / 2 : 0;
            if (k1 > kmax) k1 = kmax;
#pragma unroll
            for (int k = 0; k < 32; k++) if (k >= kdone && k < k1) sp_cvt(p[k], s[2 * k], s[2 * k + 1]);
            if (k1 > kdone) kdone = k1;
        }
        extra(e);
        if ((e + 1) % CH == 0) sched_fence();
    }
    if (E1 == 64) {
#pragma unroll
        for (int e = 64 - LAG; e < 64; e++) sp_add(s, e, l0, l1);
#pragma unroll
        for (int k = 0; k < 32; k++) if (k >= kdone) sp_cvt(p[k], s[2 * k], s[2 * k + 1]);
    }
}

__device__ __forceinline__ uint32_t qo_addr(uint32_t lane_addr, int kk) { return (lane_addr + (kk >> 2) * 1024) ^ ((kk & 3) * 32); }
__device__ __forceinline__ void load_q1(uint32_t (&q)[32], uint32_t lane_addr, int kk) {
    asm volatile("ldmatrix.sync.aligned.m8n8.x4.shared.b16 {%0,%1,%2,%3}, [%4];"
                 : "=r"(q[4 * kk]), "=r"(q[4 * kk + 1]), "=r"(q[4 * kk + 2]), "=r"(q[4 * kk + 3]) : "r"(qo_addr(lane_addr, kk)) : "memory");
}
__device__ __forceinline__ float ex2(float x) { float y; asm("ex2.approx.ftz.f32 %0, %1;" : "=f"(y) : "f"(x)); return y; }
__device__ __forceinline__ float rcp(float x) { float y; asm("rcp.approx.ftz.f32 %0, %1;" : "=f"(y) : "f"(x)); return y; }
__device__ __forceinline__ void quad_sum(float& l0, float& l1) {
    l0 += __shfl_xor_sync(0xffffffffu, l0, 1);
    l1 += __shfl_xor_sync(0xffffffffu, l1, 1);
    l0 += __shfl_xor_sync(0xffffffffu, l0, 2);
    l1 += __shfl_xor_sync(0xffffffffu, l1, 2);
}
constexpr float L_MAX = 18446744073709551616.f, L_MIN = 1.f / 65536.f;
__device__ __forceinline__ bool unsafe_sum(float l0, float l1) { return !((l0 <= L_MAX) & (l0 >= L_MIN) & (l1 <= L_MAX) & (l1 >= L_MIN)); }
__device__ __forceinline__ bool final_inv(float l0, float l1, float& i0, float& i1) {
    quad_sum(l0, l1);
    i0 = rcp(l0); i1 = rcp(l1);
    return unsafe_sum(l0, l1);
}
__device__ __forceinline__ void stage_o_part(float (&o)[64], float i0, float i1, uint32_t lane_addr, int kk, int part) {
    const float sc = (part & 1) ? i1 : i0;
    asm volatile("mul.ftz.f32 %0, %0, %1;" : "+f"(o[8 * kk + 2 * part]) : "f"(sc));
    asm volatile("mul.ftz.f32 %0, %0, %1;" : "+f"(o[8 * kk + 2 * part + 1]) : "f"(sc));
    if (part == 3) {
        uint32_t r0, r1, r2, r3;
        sp_cvt(r0, o[8 * kk + 0], o[8 * kk + 1]); sp_cvt(r1, o[8 * kk + 2], o[8 * kk + 3]);
        sp_cvt(r2, o[8 * kk + 4], o[8 * kk + 5]); sp_cvt(r3, o[8 * kk + 6], o[8 * kk + 7]);
        asm volatile("stmatrix.sync.aligned.m8n8.x4.shared.b16 [%0], {%1,%2,%3,%4};"
                     ::"r"(qo_addr(lane_addr, kk)), "r"(r0), "r"(r1), "r"(r2), "r"(r3) : "memory");
    }
}
template <int K0, int K1>
__device__ __forceinline__ void stage_o(float (&o)[64], float i0, float i1, uint32_t lane_addr) {
#pragma unroll
    for (int kk = K0; kk < K1; kk++)
#pragma unroll
        for (int part = 0; part < 4; part++) stage_o_part(o, i0, i1, lane_addr, kk, part);
}
__device__ __forceinline__ void publish_o(uint32_t bar, int lane) {
    asm volatile("fence.proxy.async.shared::cta;" ::: "memory");
    __syncwarp();
    if (lane == 0) mbar_arrive(bar);
}

#define RELEASE_K() do { if (lane == 0) mbar_arrive(bar_empty + 8 * r.st); } while (0)
#define RELEASE_V() do { if (lane == 0) mbar_arrive(bar_emptyv + 8 * r.st); } while (0)
#define PP_SYNC() bar_sync(my_bar)
#define PP_ARRIVE() bar_arrive(other_bar)

template <int N> struct Ring {
    uint32_t st, ph;
    __device__ __forceinline__ void next() { if (++st == N) { st = 0; ph ^= 1; } }
};

struct Tile { int head, qt; };
__device__ __forceinline__ Tile get_tile(int m, int it) {
    if (m >= NGRP * QT) { const int v = it * NX + m - NGRP * QT; return Tile{NREG + v / QT, v % QT}; }
    return Tile{it * NGRP + m / QT, m % QT};
}
__device__ __align__(16) float2 g_stat[NM * 128];
__device__ unsigned g_flag[NM * 2];

__device__ __forceinline__ void load_kv(uint32_t dst, const CUtensorMap* tm, uint32_t bar, int blk, Tile t) {
    if (t.head >= NREG) {
        asm volatile(
            "cp.async.bulk.tensor.4d.shared::cluster.global.mbarrier::complete_tx::bytes [%0], [%1, {%3, %3, %3, %4}], [%2];"
            ::"r"(dst), "l"(tm), "r"(bar), "r"(0), "r"(t.head * (SK / 8) + blk * 16) : "memory");
        return;
    }
    asm volatile(
        "cp.async.bulk.tensor.4d.shared::cluster.global.mbarrier::complete_tx::bytes.L2::cache_hint [%0], [%1, {%3, %3, %3, %4}], [%2], %5;"
        ::"r"(dst), "l"(tm), "r"(bar), "r"(0), "r"(t.head * (SK / 8) + blk * 16), "l"(policy_evict_first()) : "memory");
}
__device__ __forceinline__ void prefetch_kv(const CUtensorMap* tm, int blk, Tile t) {
    asm volatile("cp.async.bulk.prefetch.tensor.4d.L2.global [%0, {%1, %1, %1, %2}];"
        ::"l"(tm), "r"(0), "r"(t.head * (SK / 8) + blk * 16) : "memory");
}
__device__ __forceinline__ void prefetch_q(const CUtensorMap* tm, int row, int bh) {
    asm volatile("cp.async.bulk.prefetch.tensor.5d.L2.global [%0, {%1, %1, %1, %2, %3}];"
        ::"l"(tm), "r"(0), "r"(row >> 3), "r"(bh) : "memory");
}

__global__ void __launch_bounds__(NTHREADS, 1)
attn_kernel(const __grid_constant__ CUtensorMap tmQ, const __grid_constant__ CUtensorMap tmK,
            const __grid_constant__ CUtensorMap tmV, const __grid_constant__ CUtensorMap tmO,
            const __grid_constant__ CUtensorMap tmKh, const uint32_t zero) {
    extern __shared__ __align__(1024) uint8_t smem_raw[];
    const uint32_t smem = smem_u32(smem_raw);
    const uint32_t bar_full = smem + SM_BAR, bar_empty = bar_full + 8 * NST, bar_emptyv = bar_empty + 8 * NST;
    const uint32_t bar_q = bar_emptyv + 8 * NST, bar_o = bar_q + 16, bar_done = bar_o + 16, bar_fb = bar_done + 8;
    const uint32_t bar_tick = bar_fb + 8, bar_k0 = bar_tick + 16, sm_flag = bar_k0 + 8;
    const uint32_t bar_q0 = bar_tick, bar_ofree = bar_done;
    const bool helper = blockIdx.x < NH;
    const int cid = blockIdx.x - NH;

    if (threadIdx.x == 256) {
        mbar_init(bar_full, 1); mbar_init(bar_q, 1); mbar_init(bar_k0, 1);
        asm volatile("fence.proxy.async.shared::cta;" ::: "memory");
        if (!helper) {
            const Tile t = get_tile(cid, 0);
            mbar_expect_tx(bar_q, QO_BYTES);
            load_q_tile(smem + SM_QO, &tmQ, bar_q, t.qt * 128, t.head);
#pragma unroll 1
            for (int h = 0; h < 2; h++) {
                const uint32_t bar = h ? bar_full : bar_k0;
                mbar_expect_tx(bar, TILE_BYTES / 2);
                asm volatile(
                    "cp.async.bulk.tensor.4d.shared::cluster.global.mbarrier::complete_tx::bytes [%0], [%1, {%3, %3, %3, %4}], [%2];"
                    ::"r"(smem + h * (TILE_BYTES / 2)), "l"(&tmKh), "r"(bar), "r"(0), "r"(t.head * (SK / 8) + h * 8) : "memory");
            }
        }
        asm volatile("prefetch.tensormap [%0];" ::"l"(&tmK) : "memory");
        asm volatile("prefetch.tensormap [%0];" ::"l"(&tmV) : "memory");
        for (int i = 0; i < NST; i++) {
            if (i > 0) mbar_init(bar_full + 8 * i, 1);
            mbar_init(bar_empty + 8 * i, 8); mbar_init(bar_emptyv + 8 * i, 8);
        }
        for (int i = 0; i < 2; i++) { mbar_init(bar_o + 8 * i, 4); mbar_init(bar_tick + 8 * i, 1); }
        mbar_init(bar_q + 8, 1); mbar_init(bar_done, helper ? 1 : 2); mbar_init(bar_fb, 1);
        asm volatile("st.shared.u32 [%0], %1;" ::"r"(sm_flag), "r"(0) : "memory");
        asm volatile("fence.proxy.async.shared::cta;" ::: "memory");
    }
    __syncthreads();
    const int warp = __shfl_sync(0xffffffffu, threadIdx.x >> 5, 0);
    const int lane = threadIdx.x & 31;

    if (warp >= 8) {
        asm volatile("setmaxnreg.dec.sync.aligned.u32 24;");
        if (warp == 8) {
            if (lane == 0 && helper) {
                Ring<2> r{0, 1};
                const int m0 = blockIdx.x * NPC;
                uint32_t t0, t1;
                asm volatile("mov.u32 %0, %%globaltimer_lo;" : "=r"(t0));
                int spins = 0;
                do { __nanosleep(40); asm volatile("mov.u32 %0, %%globaltimer_lo;" : "=r"(t1)); } while (t1 - t0 < HELPER_DELAY_NS && ++spins < 200);
#pragma unroll 1
                for (int i = -1; i < HB * NPC; i++) {
                    const uint32_t full = bar_full + 8 * r.st, dst = smem + r.st * STAGE_BYTES;
                    const int nk = (i + 1) >> 1, nv = i >> 1;
                    const Tile tk = get_tile(m0 + nk, NT - 1), tv = get_tile(m0 + nv, NT - 1);
                    const bool has_v = i >= 0;
                    const bool new_k = nk < NPC && (nk == 0 || tk.head != get_tile(m0 + nk - 1, NT - 1).head);
                    const bool new_v = has_v && (nv == 0 || tv.head != get_tile(m0 + nv - 1, NT - 1).head);
                    mbar_wait_sleep(bar_empty + 8 * r.st, r.ph);
                    if (new_k) {
                        mbar_expect_tx_only(full, TILE_BYTES);
                        load_kv(dst, &tmK, full, NKB - HB + ((i + 1) & 1), tk);
                    }
                    mbar_wait_sleep(bar_emptyv + 8 * r.st, r.ph);
                    mbar_expect_tx(full, new_v ? TILE_BYTES : 0);
                    if (new_v) load_kv(dst + TILE_BYTES, &tmV, full, NKB - HB + (i & 1), tv);
                    if (has_v && nv + 2 < NPC) {
                        const Tile t = get_tile(m0 + nv + 2, NT - 1);
                        if (t.head != get_tile(m0 + nv + 1, NT - 1).head) {
                            prefetch_kv(&tmK, NKB - HB + (i & 1), t);
                            prefetch_kv(&tmV, NKB - HB + (i & 1), t);
                        }
                    }
                    r.next();
                }
            } else if (lane == 0) {
                Ring<NST> r{1, 1};
                constexpr int nsteps = NT * NKB - HB;
                Tile tv = get_tile(cid, 0), tk = tv;
                mbar_expect_tx(bar_q + 8, QO_BYTES);
                load_q_tile(smem + SM_QO + QO_BYTES, &tmQ, bar_q + 8, tv.qt * 128 + 64, tv.head);
#pragma unroll 1
                for (int i = 0; i < nsteps; i++) {
                    const uint32_t full = bar_full + 8 * r.st, dst = smem + r.st * STAGE_BYTES;
                    const bool has_k = i + 1 < nsteps;
                    if ((i & 7) == 7) tk = get_tile(cid, (i + 1) >> 3);
                    if (i == 1) mbar_wait(bar_q + 8, 0);
                    mbar_wait_sleep(bar_empty + 8 * r.st, r.ph);
                    mbar_expect_tx(full, has_k ? STAGE_BYTES : TILE_BYTES);
                    if (has_k) load_kv(dst, &tmK, full, (i + 1) & 7, tk);
                    mbar_wait_sleep(bar_emptyv + 8 * r.st, r.ph);
                    load_kv(dst + TILE_BYTES, &tmV, full, i & 7, tv);
                    if (i < (NT - 1) * NKB ? (i & 7) == QSLOT0 : i == nsteps - 2) mbar_arrive(bar_tick);
                    if (i < (NT - 1) * NKB ? (i & 7) == QSLOT1 : i == nsteps - 1) mbar_arrive(bar_tick + 8);
                    tv = tk;
                    r.next();
                }
            }
        } else if (warp < 11) {
            if (lane == 0 && helper) {
                const int w = warp - 9, m0 = blockIdx.x * NPC;
                const uint32_t qb = smem + 2 * STAGE_BYTES + w * QO_BYTES, ob = smem + SM_QO + w * QO_BYTES;
                {
                    const Tile t = get_tile(m0, NT - 1);
                    mbar_expect_tx(bar_q0 + 8 * w, QO_BYTES);
                    load_q_tile(ob, &tmQ, bar_q0 + 8 * w, t.qt * 128 + w * 64, t.head);
                }
#pragma unroll 1
                for (int n = -1; n <= NPC; n++) {
                    if (n >= 0) mbar_wait_sleep(bar_o + 8 * w, n & 1);
                    if (n > 0) {
                        const Tile t = get_tile(m0 + n - 1, NT - 1);
                        store_o_tile(ob, &tmO, t.qt * 128 + w * 64, t.head);
                        asm volatile("cp.async.bulk.global.shared::cta.bulk_group [%0], [%1], %2;"
                                     ::"l"(&g_stat[(m0 + n - 1) * 128 + w * 64]), "r"(smem + SM_ST + w * ST_BYTES), "r"(ST_BYTES) : "memory");
                        asm volatile("cp.async.bulk.commit_group;" ::: "memory");
                    }
                    if (n + 2 < NPC) {
                        const Tile t = get_tile(m0 + n + 2, NT - 1);
                        mbar_expect_tx(bar_q + 8 * w, QO_BYTES);
                        load_q_tile(qb, &tmQ, bar_q + 8 * w, t.qt * 128 + w * 64, t.head);
                    }
                    if (n + 3 < NPC) {
                        const Tile t = get_tile(m0 + n + 3, NT - 1);
                        prefetch_q(&tmQ, t.qt * 128 + w * 64, t.head);
                    }
                    if (n >= 0) {
                        asm volatile("cp.async.bulk.wait_group.read 0;" ::: "memory");
                        mbar_arrive(bar_ofree + 8 * w);
                    }
                    if (n > 0) {
                        asm volatile("cp.async.bulk.wait_group 0;" ::: "memory");
                        asm volatile("fence.proxy.async;" ::: "memory");
                        asm volatile("st.release.gpu.global.u32 [%0], %1;" ::"l"(&g_flag[(m0 + n - 1) * 2 + w]), "r"(1) : "memory");
                    }
                }
            } else if (lane == 0) {
                const int w = warp - 9;
                const uint32_t qo = smem + SM_QO + w * QO_BYTES;
                asm volatile("prefetch.tensormap [%0];" ::"l"(&tmO) : "memory");
#pragma unroll 1
                for (int it = 0; it <= NT; it++) {
                    mbar_wait_sleep(bar_o + 8 * w, it & 1);
                    if (it > 0) {
                        const Tile t = get_tile(cid, it - 1);
                        store_o_tile(qo, &tmO, t.qt * 128 + w * 64, t.head);
                        asm volatile("cp.async.bulk.commit_group;" ::: "memory");
                        asm volatile("cp.async.bulk.wait_group.read 0;" ::: "memory");
                    }
                    if (it + 1 < NT) {
                        const Tile t = get_tile(cid, it + 1);
                        mbar_wait_sleep(bar_tick + 8 * w, it & 1);
                        mbar_expect_tx(bar_q + 8 * w, QO_BYTES);
                        load_q_tile(qo, &tmQ, bar_q + 8 * w, t.qt * 128 + w * 64, t.head);
                    } else if (it + 1 == NT) {
                        const Tile t = get_tile(cid, it);
                        mbar_wait_sleep(bar_tick + 8 * w, it & 1);
                        for (uint32_t spins = 0;; spins++) {
                            unsigned f;
                            asm volatile("ld.acquire.gpu.global.u32 %0, [%1];" : "=r"(f) : "l"(&g_flag[cid * 2 + w]) : "memory");
                            if (f) break;
                            if (spins > (1u << 24)) __trap();
                            __nanosleep(100);
                        }
                        asm volatile("fence.proxy.async;" ::: "memory");
                        mbar_expect_tx(bar_q + 8 * w, QO_BYTES + ST_BYTES);
                        load_o_tile(qo, &tmO, bar_q + 8 * w, t.qt * 128 + w * 64, t.head);
                        asm volatile("cp.async.bulk.shared::cluster.global.mbarrier::complete_tx::bytes [%0], [%1], %2, [%3];"
                                     ::"r"(smem + SM_ST + w * ST_BYTES), "l"(&g_stat[cid * 128 + w * 64]), "r"(ST_BYTES), "r"(bar_q + 8 * w) : "memory");
                        g_flag[cid * 2 + w] = 0;
                    }
                }
                asm volatile("cp.async.bulk.wait_group 0;" ::: "memory");
                mbar_arrive(bar_done);
            }
        }
    } else {
        asm volatile("setmaxnreg.inc.sync.aligned.u32 240;");
        const int wg = warp >> 2;
        const uint32_t qbar = bar_q + 8 * wg, obar = bar_o + 8 * wg;
        const uint32_t lane_addr = smem + SM_QO + warp * 4096 + ((lane >> 3) & 1) * 2048 + (lane & 7) * 128 + (((lane >> 4) ^ (lane & 7)) << 4);
        const uint32_t st_addr = smem + SM_ST + (warp * 16 + (lane >> 2)) * 8;
        const int my_bar = 1 + wg, other_bar = 2 - wg;
        uint32_t redo = 0;

        float s[64], o[64];
        uint32_t p[32], q[32];
        float c0, c1, l0 = 0.f, l1 = 0.f, i0 = 0.f, i1 = 0.f;
        Fence sched_fence{(uint32_t)lane, zero & lane};
        auto none = [](int) {};
        auto stage_first = [&](int e) {
            constexpr int N = OSPLIT * 4, R = 64 - ESPLIT_B;
            const int a = (e - ESPLIT_B) * N / R, b = (e + 1 - ESPLIT_B) * N / R;
#pragma unroll
            for (int u = 0; u < N; u++) if (u >= a && u < b) stage_o_part(o, i0, i1, lane_addr, u / 4, u % 4);
        };

#define PROLOGUE(QBAR, KBAR)                                                                \
        _Pragma("unroll")                                                                   \
        for (int i = 0; i < 64; i++) o[i] = 0.f;                                            \
        if (wg == 1) bar_arrive(1);                                                         \
        mbar_wait(QBAR, 0);                                                                 \
        _Pragma("unroll")                                                                   \
        for (int kk = 0; kk < 8; kk++) load_q1(q, lane_addr, kk);                           \
        mbar_wait(KBAR, 0);                                                                 \
        PP_SYNC();                                                                          \
        fence_regs(q);                                                                      \
        wg_fence();                                                                         \
        { float t[64];                                                                      \
        issue_qk_half<0>(t, q, smem + r.st * STAGE_BYTES);                                  \
        mbar_wait(bar_full, 0);                                                             \
        issue_qk_half<1>(t, q, smem + r.st * STAGE_BYTES);                                  \
        PP_ARRIVE();                                                                        \
        wg_wait<1>();                                                                       \
        fence_half<0>(t);                                                                   \
        row_ref(t, c0, c1);                                                                 \
        if (wg == 1) bar_sync(4);                                                           \
        sched_fence();                                                                      \
        exp_pipe<0, 32 - LEAD, true>(t, p, c0, c1, l0, l1, sched_fence, none);              \
        wg_wait<0>();                                                                       \
        fence_half<1>(t); fence_regs(q);                                                    \
        RELEASE_K();                                                                        \
        RELEASE_V();                                                                        \
        r.next();                                                                           \
        exp_pipe<32 - LEAD, 64, true, 0>(t, p, c0, c1, l0, l1, sched_fence, none);          \
        fence_regs(p);                                                                      \
        }                                                                                   \
        if (wg == 0) bar_arrive(4);                                                         \
        mbar_wait(bar_full + 8 * r.st, r.ph);                                               \
        PP_SYNC();
#define STEP_HEAD()                                                                         \
        fence_regs(s); fence_regs(o); fence_regs(p); fence_regs(q);                         \
        wg_fence();                                                                         \
        issue_qk(s, q, smem + r.st * STAGE_BYTES);                                          \
        issue_pv(o, p, smem + r.st * STAGE_BYTES + TILE_BYTES, 1);                          \
        PP_ARRIVE();
#define STEP_HEAD_FIRST()                                                                   \
        fence_regs(s);                                                                      \
        wg_fence();                                                                         \
        issue_qk(s, q, smem + r.st * STAGE_BYTES);                                          \
        sched_fence();                                                                      \
        stage_o<OSPLIT, 8>(o, i0, i1, lane_addr);                                           \
        fence_regs(o); fence_regs(p);                                                       \
        wg_fence();                                                                         \
        issue_pv(o, p, smem + r.st * STAGE_BYTES + TILE_BYTES, 0);                          \
        PP_ARRIVE();
#define STEP_WAIT_QK()                                                                      \
        wg_wait<1>();                                                                       \
        fence_regs(s); fence_regs(q);                                                       \
        RELEASE_K();
#define STEP_TAIL(ES, XA, XB, POST)                                                         \
        exp_pipe<0, ES, false>(s, p, c0, c1, l0, l1, sched_fence, XA);                      \
        wg_wait<0>();                                                                       \
        fence_regs(o); fence_regs(p);                                                       \
        RELEASE_V();                                                                        \
        r.next();                                                                           \
        exp_pipe<ES, 64, true>(s, p, c0, c1, l0, l1, sched_fence, XB);                      \
        fence_regs(p);                                                                      \
        POST                                                                                \
        mbar_wait(bar_full + 8 * r.st, r.ph);                                               \
        PP_SYNC();

        if (helper) {
            const uint32_t q_addr = lane_addr - SM_QO + 2 * STAGE_BYTES;
            Ring<2> r{0, 0};
            auto put_stats = [&](float a0, float a1, float b0, float b1) {
                if ((lane & 3) == 0) {
                    asm volatile("st.shared.v2.f32 [%0], {%1, %2};" ::"r"(st_addr), "f"(a0), "f"(b0) : "memory");
                    asm volatile("st.shared.v2.f32 [%0 + 64], {%1, %2};" ::"r"(st_addr), "f"(a1), "f"(b1) : "memory");
                }
            };
            PROLOGUE(bar_q0 + 8 * wg, bar_full)
#pragma unroll 1
            for (int n = 0; n < NPC; n++) {
                {
                    STEP_HEAD_FIRST()
                    if (n + 1 < NPC) mbar_wait(qbar, n & 1);
                    STEP_WAIT_QK()
                    auto ldq = [&](int e) { if (e % 4 == 3 && e < 32) load_q1(q, q_addr, e / 4); };
                    STEP_TAIL(ESPLIT, ldq, none, publish_o(obar, lane);)
                }
                if (n + 1 < NPC) {
                    STEP_HEAD()
                    quad_sum(l0, l1);
                    i0 = rcp(l0); i1 = rcp(l1);
                    const float a0 = l0, a1 = l1, b0 = c0, b1 = c1;
                    STEP_WAIT_QK()
                    row_ref(s, c0, c1);
                    l0 = l1 = 0.f;
                    static_assert(4 * OSPLIT * 4 / (64 - ESPLIT_B) < 4, "the buffer is acquired before the first stmatrix");
                    auto sto = [&](int e) {
                        if (e == ESPLIT_B + 3) { mbar_wait(bar_ofree + 8 * wg, n & 1); put_stats(a0, a1, b0, b1); }
                        stage_first(e);
                    };
                    STEP_TAIL(ESPLIT_B, none, sto, )
                } else {
                    fence_regs(o); fence_regs(p);
                    wg_fence();
                    issue_pv(o, p, smem + r.st * STAGE_BYTES + TILE_BYTES, 1);
                    if (wg == 0) { PP_ARRIVE(); }
                    quad_sum(l0, l1);
                    i0 = rcp(l0); i1 = rcp(l1);
                    mbar_wait(bar_ofree + 8 * wg, n & 1);
                    put_stats(l0, l1, c0, c1);
                    wg_wait<0>();
                    fence_regs(o);
                    stage_o<0, 8>(o, i0, i1, lane_addr);
                    publish_o(obar, lane);
                }
            }
        } else {
            Ring<NST> r{0, 0};
            PROLOGUE(qbar, bar_k0)
#pragma unroll 1
            for (int it = 0; it < NT; it++) {
                {
                    STEP_HEAD_FIRST()
                    STEP_WAIT_QK()
                    STEP_TAIL(ESPLIT, none, none, publish_o(obar, lane);)
                }
#pragma unroll 1
                for (int j = it + 1 < NT ? 1 : HB; j < NKB - 2; j++) {
                    STEP_HEAD()
                    STEP_WAIT_QK()
                    STEP_TAIL(ESPLIT, none, none, )
                }
                if (it + 1 < NT) {
                    {
                        STEP_HEAD()
                        mbar_wait(qbar, (it + 1) & 1);
                        STEP_WAIT_QK()
                        auto ldq = [&](int e) { if (e % 4 == 3 && e < 32) load_q1(q, lane_addr, e / 4); };
                        STEP_TAIL(ESPLIT, ldq, none, )
                    }
                    {
                        STEP_HEAD()
                        if (final_inv(l0, l1, i0, i1)) redo |= 1u << it;
                        STEP_WAIT_QK()
                        row_ref(s, c0, c1);
                        l0 = l1 = 0.f;
                        STEP_TAIL(ESPLIT_B, none, stage_first, )
                    }
                } else {
                    float w0, w1, h0, h1;
                    mbar_wait(qbar, (it + 1) & 1);
                    fence_regs(o); fence_regs(p);
                    wg_fence();
                    const uint64_t desc = DESC_V | (uint64_t)(((smem + r.st * STAGE_BYTES + TILE_BYTES) & 0x3FFFFu) >> 4);
#pragma unroll
                    for (int kk = 0; kk < 8; kk++) {
                        wgmma_rs<1>(o, &p[kk * 4], desc + (uint64_t)(kk * V_STEP), 1);
                        if (kk == 0) {
                            asm volatile("ld.shared.v2.f32 {%0, %1}, [%2];" : "=f"(w0), "=f"(h0) : "r"(st_addr) : "memory");
                            asm volatile("ld.shared.v2.f32 {%0, %1}, [%2 + 64];" : "=f"(w1), "=f"(h1) : "r"(st_addr) : "memory");
#pragma unroll
                            for (int k2 = 0; k2 < 8; k2++) load_q1(q, lane_addr, k2);
                        }
                    }
                    wg_commit();
                    sched_fence();
                    if (wg == 0) { PP_ARRIVE(); }
                    quad_sum(l0, l1);
                    const bool bad = unsafe_sum(w0, w1) | unsafe_sum(l0, l1);
                    w0 *= ex2(c0 - h0); w1 *= ex2(c1 - h1);
                    l0 += w0; l1 += w1;
                    redo |= (uint32_t)(bad | unsafe_sum(l0, l1)) << it;
                    i0 = rcp(l0); i1 = rcp(l1);
#pragma unroll
                    for (int k = 0; k < 32; k++) {
                        s[2 * k] = __uint_as_float(q[k] * (65536u + zero));
                        s[2 * k + 1] = __uint_as_float(q[k] & 0xffff0000u);
                    }
                    fence_regs(s);
                    sched_fence();
                    wg_wait<0>();
                    fence_regs(o);
#pragma unroll
                    for (int kk = 0; kk < 8; kk++) {
                        uint32_t rr[4];
#pragma unroll
                        for (int u = 0; u < 4; u++) {
                            const int e = 8 * kk + 2 * u;
                            const float sc = (u & 1) ? i1 : i0, wc = (u & 1) ? w1 : w0;
                            sp_cvt(rr[u], fmaf(s[e], wc, o[e]) * sc, fmaf(s[e + 1], wc, o[e + 1]) * sc);
                        }
                        asm volatile("stmatrix.sync.aligned.m8n8.x4.shared.b16 [%0], {%1,%2,%3,%4};"
                                     ::"r"(qo_addr(lane_addr, kk)), "r"(rr[0]), "r"(rr[1]), "r"(rr[2]), "r"(rr[3]) : "memory");
                    }
                    publish_o(obar, lane);
                }
            }

            if (redo) asm volatile("red.shared.or.b32 [%0], %1;" ::"r"(sm_flag), "r"(redo) : "memory");
            bar_sync(3);
            asm volatile("ld.shared.u32 %0, [%1];" : "=r"(redo) : "r"(sm_flag) : "memory");
            redo = __shfl_sync(0xffffffffu, redo, 0);
            if (redo) {
                mbar_wait(bar_done, 0);
                uint32_t ph = 0;
#pragma unroll 1
                for (int it = 0; it < NT; it++) {
                    if (!((redo >> it) & 1)) continue;
                    const Tile t = get_tile(cid, it);
                    float m0 = -INFINITY, m1 = -INFINITY;
                    l0 = l1 = 0.f;
#pragma unroll
                    for (int i = 0; i < 64; i++) o[i] = 0.f;
#pragma unroll 1
                    for (int j = 0; j < NKB; j++) {
                        if (threadIdx.x == 0) {
                            mbar_expect_tx(bar_fb, j == 0 ? STAGE_BYTES + 2 * QO_BYTES : STAGE_BYTES);
                            if (j == 0)
                                for (int w = 0; w < 2; w++) load_q_tile(smem + SM_QO + w * QO_BYTES, &tmQ, bar_fb, t.qt * 128 + w * 64, t.head);
                            load_kv(smem, &tmK, bar_fb, j, t);
                            load_kv(smem + TILE_BYTES, &tmV, bar_fb, j, t);
                        }
                        __syncwarp();
                        mbar_wait(bar_fb, ph); ph ^= 1;
#pragma unroll
                        for (int kk = 0; kk < 8; kk++) load_q1(q, lane_addr, kk);
                        fence_regs(q); fence_regs(s);
                        wg_fence();
                        issue_qk(s, q, smem);
                        wg_wait<0>();
                        fence_regs(s);
                        float x0 = m0, x1 = m1;
#pragma unroll
                        for (int i = 0; i < 16; i++) {
                            x0 = fmaxf(x0, fmaxf(s[4 * i], s[4 * i + 1]));
                            x1 = fmaxf(x1, fmaxf(s[4 * i + 2], s[4 * i + 3]));
                        }
                        x0 = fmaxf(x0, __shfl_xor_sync(0xffffffffu, x0, 1)); x1 = fmaxf(x1, __shfl_xor_sync(0xffffffffu, x1, 1));
                        x0 = fmaxf(x0, __shfl_xor_sync(0xffffffffu, x0, 2)); x1 = fmaxf(x1, __shfl_xor_sync(0xffffffffu, x1, 2));
                        const float r0 = x0 == -INFINITY ? 0.f : x0, r1 = x1 == -INFINITY ? 0.f : x1;
                        const float a0 = ex2((m0 - r0) * SCALE_LOG2), a1 = ex2((m1 - r1) * SCALE_LOG2);
                        m0 = x0; m1 = x1;
                        l0 *= a0; l1 *= a1;
#pragma unroll
                        for (int i = 0; i < 64; i++) {
                            s[i] = ex2((s[i] - ((i & 2) ? r1 : r0)) * SCALE_LOG2);
                            if (i & 2) l1 += s[i]; else l0 += s[i];
                            o[i] *= (i & 2) ? a1 : a0;
                        }
#pragma unroll
                        for (int k = 0; k < 32; k++) sp_cvt(p[k], s[2 * k], s[2 * k + 1]);
                        fence_regs(o); fence_regs(p);
                        wg_fence();
                        issue_pv(o, p, smem + TILE_BYTES, 1);
                        wg_wait<0>();
                        fence_regs(o);
                        bar_sync(3);
                    }
                    final_inv(l0, l1, i0, i1);
                    stage_o<0, 8>(o, i0, i1, lane_addr);
                    asm volatile("fence.proxy.async.shared::cta;" ::: "memory");
                    bar_sync(3);
                    if (threadIdx.x == 0) {
                        for (int w = 0; w < 2; w++) store_o_tile(smem + SM_QO + w * QO_BYTES, &tmO, t.qt * 128 + w * 64, t.head);
                        asm volatile("cp.async.bulk.commit_group;" ::: "memory");
                        asm volatile("cp.async.bulk.wait_group 0;" ::: "memory");
                    }
                    __syncwarp();
                }
            }
        }
        if (zero) asm volatile("st.shared.u32 [%0], %1;" ::"r"(lane_addr), "r"(sched_fence.t) : "memory");
    }
}

typedef CUresult (*EncodeFn)(CUtensorMap*, CUtensorMapDataType, cuuint32_t, void*, const cuuint64_t*, const cuuint64_t*,
                             const cuuint32_t*, const cuuint32_t*, CUtensorMapInterleave, CUtensorMapSwizzle,
                             CUtensorMapL2promotion, CUtensorMapFloatOOBfill);

void make_qo_map(EncodeFn enc, CUtensorMap* tm, void* ptr, int box_groups) {
    cuuint64_t dims[5] = {64, 8, 2, SQ / 8, BH};
    cuuint64_t strides[4] = {HD * 2, 128, 8 * HD * 2, (cuuint64_t)SQ * HD * 2};
    cuuint32_t box[5] = {64, 8, 2, (cuuint32_t)box_groups, 1};
    cuuint32_t es[5] = {1, 1, 1, 1, 1};
    enc(tm, CU_TENSOR_MAP_DATA_TYPE_BFLOAT16, 5, ptr, dims, strides, box, es, CU_TENSOR_MAP_INTERLEAVE_NONE,
        CU_TENSOR_MAP_SWIZZLE_128B, CU_TENSOR_MAP_L2_PROMOTION_NONE, CU_TENSOR_MAP_FLOAT_OOB_FILL_NONE);
}

void make_kv_map(EncodeFn enc, CUtensorMap* tm, void* ptr, int box_groups) {
    cuuint64_t dims[4] = {64, 8, 2, (cuuint64_t)BH * SK / 8};
    cuuint64_t strides[3] = {HD * 2, 128, 8 * HD * 2};
    cuuint32_t box[4] = {64, 8, 2, (cuuint32_t)box_groups};
    cuuint32_t es[4] = {1, 1, 1, 1};
    enc(tm, CU_TENSOR_MAP_DATA_TYPE_BFLOAT16, 4, ptr, dims, strides, box, es, CU_TENSOR_MAP_INTERLEAVE_NONE,
        CU_TENSOR_MAP_SWIZZLE_128B, CU_TENSOR_MAP_L2_PROMOTION_NONE, CU_TENSOR_MAP_FLOAT_OOB_FILL_NONE);
}

}

extern "C" void kernel_launch(void* const* d_in, const int* in_sizes, int n_in, void* d_out, int out_size) {
    static EncodeFn enc = nullptr;
    if (!enc) {
        void* fn = nullptr;
        cudaDriverEntryPointQueryResult qr;
        cudaGetDriverEntryPoint("cuTensorMapEncodeTiled", &fn, cudaEnableDefault, &qr);
        enc = (EncodeFn)fn;
        cudaFuncSetAttribute(attn_kernel, cudaFuncAttributeMaxDynamicSharedMemorySize, SMEM_BYTES);
    }
    CUtensorMap tq, tk, tv, to, tkh;
    make_qo_map(enc, &tq, d_in[0], 8);
    make_kv_map(enc, &tk, d_in[1], 16);
    make_kv_map(enc, &tkh, d_in[1], 8);
    make_kv_map(enc, &tv, d_in[2], 16);
    make_qo_map(enc, &to, d_out, 8);
    attn_kernel<<<NH + NM, NTHREADS, SMEM_BYTES, cudaStreamPerThread>>>(tq, tk, tv, to, tkh, 0u);
}
```
